```python
import torch

def _softmax(x, axis=-1):
    return torch.softmax(x, dim=axis)
def _gelu(x):
    return torch.nn.functional.gelu(x, approximate="tanh")
def _silu(x):
    return torch.nn.functional.silu(x)
def _sigmoid(x):
    return torch.sigmoid(x)
def _layernorm(x, axis=-1, eps=1e-5):
    m = x.mean(dim=axis, keepdim=True)
    v = x.var(dim=axis, keepdim=True, unbiased=False)
    return (x - m) / torch.sqrt(v + eps)
def _scatter_add(tgt, idx, src, axis=0):
    return tgt.clone().index_add_(axis, idx, src)
def _segment_sum(src, seg, n):
    out = torch.zeros((n,) + src.shape[1:], dtype=src.dtype)
    return out.index_add_(0, seg, src)
def _pad(x, pw):
    flat = tuple(v for pair in reversed(pw) for v in pair)
    return torch.nn.functional.pad(x, flat)

kernel_name = 'parallel_sum__sliding_local_dilated__glu_gated_reglu__prompt'

def setup_inputs():

    _w = (lambda a: (lambda t: t.to(torch.bfloat16) if t.is_floating_point() else t)(torch.as_tensor(a)))
    def _A_setup():
        B, S, D = 1, 2048, 576
        return {
            "x": _w((lambda *s: torch.randn(*s, dtype=torch.bfloat16) * 0.05)(B, S, D)),
            "wqkv": _w((lambda *s: torch.randn(*s, dtype=torch.bfloat16) * 0.05)(D, 3 * D)),
            "wo": _w((lambda *s: torch.randn(*s, dtype=torch.bfloat16) * 0.05)(D, D)),
        }
    _A_in = _A_setup()

    def _B_setup():
        B, S, D, F = 1, 2048, 576, 4608
        return {
            "x": _w((lambda *s: torch.randn(*s, dtype=torch.bfloat16) * 0.05)(B, S, D)),
            "W_gate": _w((lambda *s: torch.randn(*s, dtype=torch.bfloat16) * 0.8)(D, F) * (2.0 / D) ** 0.5),
            "W_up": _w((lambda *s: torch.randn(*s, dtype=torch.bfloat16) * 0.8)(D, F) * (2.0 / D) ** 0.5),
            "W_down": _w((lambda *s: torch.randn(*s, dtype=torch.bfloat16) * 0.8)(F, D) * (1.0 / F) ** 0.5),
        }
    _B_in = _B_setup()

    return {
        "A_x": _A_in["x"],
        "A_wqkv": _A_in["wqkv"],
        "A_wo": _A_in["wo"],
        "B_x": _B_in["x"],
        "B_W_gate": _B_in["W_gate"],
        "B_W_up": _B_in["W_up"],
        "B_W_down": _B_in["W_down"],
    }

def reference(A_x, A_wqkv, A_wo, B_x, B_W_gate, B_W_up, B_W_down):
    def _A_ref(x, wqkv, wo):
        B, S, D = x.shape
        H = 32; Dh = D // H
        W, dil = 8, 2
        qkv = (lambda x, *d: x.permute(*d))((x @ wqkv).reshape(B, S, 3, H, Dh), 2, 0, 3, 1, 4)
        q, k, v = qkv[0], qkv[1], qkv[2]
        scale = Dh ** -0.5
        pos = torch.arange(S)
        off = torch.arange(W) * dil
        idx = pos[:, None] - off[None, :]
        mask = idx >= 0
        idx_c = torch.where(mask, idx, 0).reshape(-1)
        kg = k[:, :, idx_c, :].reshape(B, H, S, W, Dh)
        vg = v[:, :, idx_c, :].reshape(B, H, S, W, Dh)
        logits = torch.einsum("bhsd,bhswd->bhsw", q, kg) * scale
        logits = torch.where(mask[None, None, :, :], logits, -1e9)
        attn = _softmax(logits, axis=-1)
        o = torch.einsum("bhsw,bhswd->bhsd", attn, vg)
        return (lambda x, *d: x.permute(*d))(o, 0, 2, 1, 3).reshape(B, S, D) @ wo

    def _B_ref(x, W_gate, W_up, W_down):
        gate = torch.einsum("bsd,df->bsf", x, W_gate)
        up = torch.einsum("bsd,df->bsf", x, W_up)
        gate = gate * (lambda x, dt: x.to(dt))(gate > 0, gate.dtype)
        h = gate * up
        return torch.einsum("bsf,fd->bsd", h, W_down)

    x = A_x
    xn = _layernorm(x, axis=-1)
    return x + _A_ref(xn, A_wqkv, A_wo) + _B_ref(xn, B_W_gate, B_W_up, B_W_down)
```

```cpp
#include <cuda_runtime.h>
#include <cuda_bf16.h>
#include <cuda.h>
#include <stdint.h>

#define S_LEN 2048
#define DM 576
#define FF 4608
#define NQKV 1728

__device__ __align__(1024) __nv_bfloat16 g_h[(size_t)S_LEN * FF];
__device__ __align__(1024) __nv_bfloat16 g_halo[(size_t)128 * 2304];
__device__ __align__(1024) __nv_bfloat16 g_o[(size_t)S_LEN * DM];
__device__ __align__(1024) float g_part[(size_t)32 * 4 * 128 * 288];
__device__ unsigned int g_flag[128];
__device__ unsigned int g_cnt[32];

#define TL(k, e)
__device__ __forceinline__ uint32_t smem_u32(const void* p) { return (uint32_t)__cvta_generic_to_shared(p); }

__device__ __forceinline__ void mbar_init(uint32_t bar, uint32_t count) {
  asm volatile("mbarrier.init.shared::cta.b64 [%0], %1;" ::"r"(bar), "r"(count));
}
__device__ __forceinline__ void mbar_arrive(uint32_t bar) {
  asm volatile("mbarrier.arrive.shared::cta.b64 _, [%0];" ::"r"(bar) : "memory");
}
__device__ __forceinline__ void mbar_expect_tx(uint32_t bar, uint32_t bytes) {
  asm volatile("mbarrier.arrive.expect_tx.shared::cta.b64 _, [%0], %1;" ::"r"(bar), "r"(bytes) : "memory");
}
__device__ __forceinline__ void mbar_wait(uint32_t bar, uint32_t parity) {
  uint32_t done;
  uint32_t spins = 0;
  do {
    asm volatile(
        "{\n.reg .pred p;\n"
        "mbarrier.try_wait.parity.shared::cta.b64 p, [%1], %2;\n"
        "selp.u32 %0, 1, 0, p;\n}\n"
        : "=r"(done) : "r"(bar), "r"(parity) : "memory");
    if (++spins > (1u << 20)) break;
  } while (!done);
}
__device__ __forceinline__ bool mbar_test(uint32_t bar, uint32_t parity) {
  uint32_t done;
  asm volatile(
      "{\n.reg .pred p;\n"
      "mbarrier.test_wait.parity.shared::cta.b64 p, [%1], %2;\n"
      "selp.u32 %0, 1, 0, p;\n}\n"
      : "=r"(done) : "r"(bar), "r"(parity) : "memory");
  return done != 0;
}
__device__ __forceinline__ void tma_load_2d(uint32_t dst, const CUtensorMap* map, int c0, int c1, uint32_t bar) {
  asm volatile(
      "cp.async.bulk.tensor.2d.shared::cluster.global.mbarrier::complete_tx::bytes [%0], [%1, {%3, %4}], [%2];"
      ::"r"(dst), "l"((uint64_t)map), "r"(bar), "r"(c0), "r"(c1) : "memory");
}
__device__ __forceinline__ void tma_load_2d_mc(uint32_t dst, const CUtensorMap* map, int c0, int c1, uint32_t bar) {
  asm volatile(
      "cp.async.bulk.tensor.2d.shared::cluster.global.mbarrier::complete_tx::bytes.multicast::cluster [%0], [%1, {%3, %4}], [%2], %5;"
      ::"r"(dst), "l"((uint64_t)map), "r"(bar), "r"(c0), "r"(c1), "h"((uint16_t)3) : "memory");
}
__device__ __forceinline__ void mbar_arrive_both(uint32_t bar, uint32_t peer) {
  uint32_t ra;
  asm volatile("mapa.shared::cluster.u32 %0, %1, %2;" : "=r"(ra) : "r"(bar), "r"(peer));
  asm volatile("mbarrier.arrive.shared::cta.b64 _, [%0];" ::"r"(bar) : "memory");
  asm volatile("mbarrier.arrive.shared::cluster.b64 _, [%0];" ::"r"(ra) : "memory");
}
__device__ __forceinline__ void cluster_sync_all() {
  asm volatile("barrier.cluster.arrive.release.aligned;\nbarrier.cluster.wait.acquire.aligned;" ::: "memory");
}
__device__ __forceinline__ void bulk_load_1d(uint32_t dst, const void* src, uint32_t bytes, uint32_t bar) {
  asm volatile("cp.async.bulk.shared::cluster.global.mbarrier::complete_tx::bytes [%0], [%1], %2, [%3];"
               ::"r"(dst), "l"(src), "r"(bytes), "r"(bar) : "memory");
}
__device__ __forceinline__ void tma_load_5d_mc(uint32_t dst, const CUtensorMap* map, int c0, int c4, uint32_t bar) {
  asm volatile(
      "cp.async.bulk.tensor.5d.shared::cluster.global.mbarrier::complete_tx::bytes.multicast::cluster [%0], [%1, {%3, %5, %5, %5, %4}], [%2], %6;"
      ::"r"(dst), "l"((uint64_t)map), "r"(bar), "r"(c0), "r"(c4), "r"(0), "h"((uint16_t)3) : "memory");
}
__device__ __forceinline__ void tma_prefetch_2d(const CUtensorMap* map, int c0, int c1) {
  asm volatile("cp.async.bulk.prefetch.tensor.2d.L2.global.tile [%0, {%1, %2}];" ::"l"((uint64_t)map), "r"(c0), "r"(c1) : "memory");
}
__device__ __forceinline__ void fence_async_all() { asm volatile("fence.proxy.async;" ::: "memory"); }
__device__ __forceinline__ void tma_store_2d(const CUtensorMap* map, uint32_t src, int c0, int c1) {
  asm volatile("cp.async.bulk.tensor.2d.global.shared::cta.bulk_group [%0, {%2, %3}], [%1];"
               ::"l"((uint64_t)map), "r"(src), "r"(c0), "r"(c1) : "memory");
}
__device__ __forceinline__ void bulk_commit() { asm volatile("cp.async.bulk.commit_group;" ::: "memory"); }
__device__ __forceinline__ void bulk_wait_read0() { asm volatile("cp.async.bulk.wait_group.read 0;" ::: "memory"); }
__device__ __forceinline__ void bulk_wait0() { asm volatile("cp.async.bulk.wait_group 0;" ::: "memory"); }
__device__ __forceinline__ void fence_async_smem() { asm volatile("fence.proxy.async.shared::cta;" ::: "memory"); }
__device__ __forceinline__ void wgmma_fence() { asm volatile("wgmma.fence.sync.aligned;" ::: "memory"); }
__device__ __forceinline__ void wgmma_commit() { asm volatile("wgmma.commit_group.sync.aligned;" ::: "memory"); }
template <int N> __device__ __forceinline__ void wgmma_wait() { asm volatile("wgmma.wait_group.sync.aligned %0;" ::"n"(N) : "memory"); }
__device__ __forceinline__ void named_bar_sync(int id, int n) { asm volatile("bar.sync %0, %1;" ::"r"(id), "r"(n) : "memory"); }
__device__ __forceinline__ void prefetch_tmap(const CUtensorMap* m) {
  asm volatile("prefetch.tensormap [%0];" ::"l"((uint64_t)m) : "memory");
}
__device__ __forceinline__ uint32_t make_desc(uint32_t addr, uint32_t lbo_bytes, uint32_t) {
  return ((addr & 0x3FFFF) >> 4) | ((lbo_bytes >> 4) << 16);
}
__device__ __forceinline__ uint32_t pack_bf16(float a, float b) {
  __nv_bfloat162 t = __floats2bfloat162_rn(a, b);
  return *reinterpret_cast<uint32_t*>(&t);
}
__device__ __forceinline__ void stmatrix_x4(uint32_t addr, uint32_t r0, uint32_t r1, uint32_t r2, uint32_t r3) {
  asm volatile("stmatrix.sync.aligned.m8n8.x4.shared.b16 [%0], {%1, %2, %3, %4};"
               ::"r"(addr), "r"(r0), "r"(r1), "r"(r2), "r"(r3) : "memory");
}

__device__ __forceinline__ void l2_prefetch(const void* p, uint32_t bytes) {
  asm volatile("cp.async.bulk.prefetch.L2.global [%0], %1;" ::"l"(p), "r"(bytes) : "memory");
}
__device__ __forceinline__ unsigned int ld_acquire(const unsigned int* p) {
  unsigned int v;
  asm volatile("ld.acquire.gpu.global.u32 %0, [%1];" : "=r"(v) : "l"(p) : "memory");
  return v;
}
__device__ __forceinline__ uint32_t ld_acquire_smem(uint32_t a) {
  uint32_t v;
  asm volatile("ld.acquire.cta.shared::cta.u32 %0, [%1];" : "=r"(v) : "r"(a) : "memory");
  return v;
}
__device__ __forceinline__ void wait_flag(const unsigned int* p, unsigned int v) {
  uint32_t spins = 0;
  while (ld_acquire(p) != v) { if (++spins > (1u << 22)) break; }
}
__device__ __forceinline__ void st_release(unsigned int* p, unsigned int v) {
  asm volatile("st.release.gpu.global.u32 [%0], %1;" ::"l"(p), "r"(v) : "memory");
}
__device__ __forceinline__ void red_release_add(unsigned int* p, unsigned int v) {
  asm volatile("red.release.gpu.global.add.u32 [%0], %1;" ::"l"(p), "r"(v) : "memory");
}
__device__ __forceinline__ float bf_lo(uint32_t w) { return __uint_as_float(w << 16); }
__device__ __forceinline__ float bf_hi(uint32_t w) { return __uint_as_float(w & 0xffff0000u); }

__device__ __forceinline__ void wgmma_n72(float (&d)[36], uint32_t da, uint32_t db, int scaleD) {
  asm volatile("{\n.reg .pred p;\n.reg .b64 ra, rb;\n.reg .b32 hi;\nsetp.ne.b32 p, %38, 0;\nmov.b32 hi, 0x40000040;\n"
    "mov.b64 ra, {%36, hi};\nmov.b64 rb, {%37, hi};\n"
    "wgmma.mma_async.sync.aligned.m64n72k16.f32.bf16.bf16 {%0,%1,%2,%3,%4,%5,%6,%7,%8,%9,%10,%11,%12,%13,%14,%15,%16,%17,%18,%19,%20,%21,%22,%23,%24,%25,%26,%27,%28,%29,%30,%31,%32,%33,%34,%35}, ra, rb, p, 1, 1, 0, 1;\n}\n"
    : "+f"(d[0]),"+f"(d[1]),"+f"(d[2]),"+f"(d[3]),"+f"(d[4]),"+f"(d[5]),"+f"(d[6]),"+f"(d[7]),"+f"(d[8]),"+f"(d[9]),"+f"(d[10]),"+f"(d[11]),"+f"(d[12]),"+f"(d[13]),"+f"(d[14]),"+f"(d[15]),"+f"(d[16]),"+f"(d[17]),"+f"(d[18]),"+f"(d[19]),"+f"(d[20]),"+f"(d[21]),"+f"(d[22]),"+f"(d[23]),"+f"(d[24]),"+f"(d[25]),"+f"(d[26]),"+f"(d[27]),"+f"(d[28]),"+f"(d[29]),"+f"(d[30]),"+f"(d[31]),"+f"(d[32]),"+f"(d[33]),"+f"(d[34]),"+f"(d[35])
    : "r"(da), "r"(db), "r"(scaleD));
}

__device__ __forceinline__ void wgmma_n96(float (&d)[48], uint32_t da, uint32_t db, int scaleD) {
  asm volatile("{\n.reg .pred p;\n.reg .b64 ra, rb;\n.reg .b32 hi;\nsetp.ne.b32 p, %50, 0;\nmov.b32 hi, 0x40000040;\n"
    "mov.b64 ra, {%48, hi};\nmov.b64 rb, {%49, hi};\n"
    "wgmma.mma_async.sync.aligned.m64n96k16.f32.bf16.bf16 {%0,%1,%2,%3,%4,%5,%6,%7,%8,%9,%10,%11,%12,%13,%14,%15,%16,%17,%18,%19,%20,%21,%22,%23,%24,%25,%26,%27,%28,%29,%30,%31,%32,%33,%34,%35,%36,%37,%38,%39,%40,%41,%42,%43,%44,%45,%46,%47}, ra, rb, p, 1, 1, 0, 1;\n}\n"
    : "+f"(d[0]),"+f"(d[1]),"+f"(d[2]),"+f"(d[3]),"+f"(d[4]),"+f"(d[5]),"+f"(d[6]),"+f"(d[7]),"+f"(d[8]),"+f"(d[9]),"+f"(d[10]),"+f"(d[11]),"+f"(d[12]),"+f"(d[13]),"+f"(d[14]),"+f"(d[15]),"+f"(d[16]),"+f"(d[17]),"+f"(d[18]),"+f"(d[19]),"+f"(d[20]),"+f"(d[21]),"+f"(d[22]),"+f"(d[23]),"+f"(d[24]),"+f"(d[25]),"+f"(d[26]),"+f"(d[27]),"+f"(d[28]),"+f"(d[29]),"+f"(d[30]),"+f"(d[31]),"+f"(d[32]),"+f"(d[33]),"+f"(d[34]),"+f"(d[35]),"+f"(d[36]),"+f"(d[37]),"+f"(d[38]),"+f"(d[39]),"+f"(d[40]),"+f"(d[41]),"+f"(d[42]),"+f"(d[43]),"+f"(d[44]),"+f"(d[45]),"+f"(d[46]),"+f"(d[47])
    : "r"(da), "r"(db), "r"(scaleD));
}

__device__ __forceinline__ void wgmma_n128(float (&d)[64], uint32_t da, uint32_t db, int scaleD) {
  asm volatile("{\n.reg .pred p;\n.reg .b64 ra, rb;\n.reg .b32 hi;\nsetp.ne.b32 p, %66, 0;\nmov.b32 hi, 0x40000040;\n"
    "mov.b64 ra, {%64, hi};\nmov.b64 rb, {%65, hi};\n"
    "wgmma.mma_async.sync.aligned.m64n128k16.f32.bf16.bf16 {%0,%1,%2,%3,%4,%5,%6,%7,%8,%9,%10,%11,%12,%13,%14,%15,%16,%17,%18,%19,%20,%21,%22,%23,%24,%25,%26,%27,%28,%29,%30,%31,%32,%33,%34,%35,%36,%37,%38,%39,%40,%41,%42,%43,%44,%45,%46,%47,%48,%49,%50,%51,%52,%53,%54,%55,%56,%57,%58,%59,%60,%61,%62,%63}, ra, rb, p, 1, 1, 0, 1;\n}\n"
    : "+f"(d[0]),"+f"(d[1]),"+f"(d[2]),"+f"(d[3]),"+f"(d[4]),"+f"(d[5]),"+f"(d[6]),"+f"(d[7]),"+f"(d[8]),"+f"(d[9]),"+f"(d[10]),"+f"(d[11]),"+f"(d[12]),"+f"(d[13]),"+f"(d[14]),"+f"(d[15]),"+f"(d[16]),"+f"(d[17]),"+f"(d[18]),"+f"(d[19]),"+f"(d[20]),"+f"(d[21]),"+f"(d[22]),"+f"(d[23]),"+f"(d[24]),"+f"(d[25]),"+f"(d[26]),"+f"(d[27]),"+f"(d[28]),"+f"(d[29]),"+f"(d[30]),"+f"(d[31]),"+f"(d[32]),"+f"(d[33]),"+f"(d[34]),"+f"(d[35]),"+f"(d[36]),"+f"(d[37]),"+f"(d[38]),"+f"(d[39]),"+f"(d[40]),"+f"(d[41]),"+f"(d[42]),"+f"(d[43]),"+f"(d[44]),"+f"(d[45]),"+f"(d[46]),"+f"(d[47]),"+f"(d[48]),"+f"(d[49]),"+f"(d[50]),"+f"(d[51]),"+f"(d[52]),"+f"(d[53]),"+f"(d[54]),"+f"(d[55]),"+f"(d[56]),"+f"(d[57]),"+f"(d[58]),"+f"(d[59]),"+f"(d[60]),"+f"(d[61]),"+f"(d[62]),"+f"(d[63])
    : "r"(da), "r"(db), "r"(scaleD));
}

__device__ __forceinline__ void wgmma_n192(float (&d)[96], uint32_t da, uint32_t db, int scaleD) {
  asm volatile("{\n.reg .pred p;\n.reg .b64 ra, rb;\n.reg .b32 hi;\nsetp.ne.b32 p, %98, 0;\nmov.b32 hi, 0x40000040;\n"
    "mov.b64 ra, {%96, hi};\nmov.b64 rb, {%97, hi};\n"
    "wgmma.mma_async.sync.aligned.m64n192k16.f32.bf16.bf16 {%0,%1,%2,%3,%4,%5,%6,%7,%8,%9,%10,%11,%12,%13,%14,%15,%16,%17,%18,%19,%20,%21,%22,%23,%24,%25,%26,%27,%28,%29,%30,%31,%32,%33,%34,%35,%36,%37,%38,%39,%40,%41,%42,%43,%44,%45,%46,%47,%48,%49,%50,%51,%52,%53,%54,%55,%56,%57,%58,%59,%60,%61,%62,%63,%64,%65,%66,%67,%68,%69,%70,%71,%72,%73,%74,%75,%76,%77,%78,%79,%80,%81,%82,%83,%84,%85,%86,%87,%88,%89,%90,%91,%92,%93,%94,%95}, ra, rb, p, 1, 1, 0, 1;\n}\n"
    : "+f"(d[0]),"+f"(d[1]),"+f"(d[2]),"+f"(d[3]),"+f"(d[4]),"+f"(d[5]),"+f"(d[6]),"+f"(d[7]),"+f"(d[8]),"+f"(d[9]),"+f"(d[10]),"+f"(d[11]),"+f"(d[12]),"+f"(d[13]),"+f"(d[14]),"+f"(d[15]),"+f"(d[16]),"+f"(d[17]),"+f"(d[18]),"+f"(d[19]),"+f"(d[20]),"+f"(d[21]),"+f"(d[22]),"+f"(d[23]),"+f"(d[24]),"+f"(d[25]),"+f"(d[26]),"+f"(d[27]),"+f"(d[28]),"+f"(d[29]),"+f"(d[30]),"+f"(d[31]),"+f"(d[32]),"+f"(d[33]),"+f"(d[34]),"+f"(d[35]),"+f"(d[36]),"+f"(d[37]),"+f"(d[38]),"+f"(d[39]),"+f"(d[40]),"+f"(d[41]),"+f"(d[42]),"+f"(d[43]),"+f"(d[44]),"+f"(d[45]),"+f"(d[46]),"+f"(d[47]),"+f"(d[48]),"+f"(d[49]),"+f"(d[50]),"+f"(d[51]),"+f"(d[52]),"+f"(d[53]),"+f"(d[54]),"+f"(d[55]),"+f"(d[56]),"+f"(d[57]),"+f"(d[58]),"+f"(d[59]),"+f"(d[60]),"+f"(d[61]),"+f"(d[62]),"+f"(d[63]),"+f"(d[64]),"+f"(d[65]),"+f"(d[66]),"+f"(d[67]),"+f"(d[68]),"+f"(d[69]),"+f"(d[70]),"+f"(d[71]),"+f"(d[72]),"+f"(d[73]),"+f"(d[74]),"+f"(d[75]),"+f"(d[76]),"+f"(d[77]),"+f"(d[78]),"+f"(d[79]),"+f"(d[80]),"+f"(d[81]),"+f"(d[82]),"+f"(d[83]),"+f"(d[84]),"+f"(d[85]),"+f"(d[86]),"+f"(d[87]),"+f"(d[88]),"+f"(d[89]),"+f"(d[90]),"+f"(d[91]),"+f"(d[92]),"+f"(d[93]),"+f"(d[94]),"+f"(d[95])
    : "r"(da), "r"(db), "r"(scaleD));
}

__device__ __forceinline__ void wgmma_rs_n72(float (&d)[36], const uint32_t (&a)[4], uint32_t db, int scaleD) {
  asm volatile("{\n.reg .pred p;\n.reg .b64 rb;\n.reg .b32 hi;\nsetp.ne.b32 p, %41, 0;\nmov.b32 hi, 0x40000040;\n"
    "mov.b64 rb, {%40, hi};\n"
    "wgmma.mma_async.sync.aligned.m64n72k16.f32.bf16.bf16 {%0,%1,%2,%3,%4,%5,%6,%7,%8,%9,%10,%11,%12,%13,%14,%15,%16,%17,%18,%19,%20,%21,%22,%23,%24,%25,%26,%27,%28,%29,%30,%31,%32,%33,%34,%35}, {%36,%37,%38,%39}, rb, p, 1, 1, 1;\n}\n"
    : "+f"(d[0]),"+f"(d[1]),"+f"(d[2]),"+f"(d[3]),"+f"(d[4]),"+f"(d[5]),"+f"(d[6]),"+f"(d[7]),"+f"(d[8]),"+f"(d[9]),"+f"(d[10]),"+f"(d[11]),"+f"(d[12]),"+f"(d[13]),"+f"(d[14]),"+f"(d[15]),"+f"(d[16]),"+f"(d[17]),"+f"(d[18]),"+f"(d[19]),"+f"(d[20]),"+f"(d[21]),"+f"(d[22]),"+f"(d[23]),"+f"(d[24]),"+f"(d[25]),"+f"(d[26]),"+f"(d[27]),"+f"(d[28]),"+f"(d[29]),"+f"(d[30]),"+f"(d[31]),"+f"(d[32]),"+f"(d[33]),"+f"(d[34]),"+f"(d[35])
    : "r"(a[0]), "r"(a[1]), "r"(a[2]), "r"(a[3]), "r"(db), "r"(scaleD));
}

__device__ __forceinline__ void wgmma_rs_n128(float (&d)[64], const uint32_t (&a)[4], uint32_t db, int scaleD) {
  asm volatile("{\n.reg .pred p;\n.reg .b64 rb;\n.reg .b32 hi;\nsetp.ne.b32 p, %69, 0;\nmov.b32 hi, 0x40000040;\n"
    "mov.b64 rb, {%68, hi};\n"
    "wgmma.mma_async.sync.aligned.m64n128k16.f32.bf16.bf16 {%0,%1,%2,%3,%4,%5,%6,%7,%8,%9,%10,%11,%12,%13,%14,%15,%16,%17,%18,%19,%20,%21,%22,%23,%24,%25,%26,%27,%28,%29,%30,%31,%32,%33,%34,%35,%36,%37,%38,%39,%40,%41,%42,%43,%44,%45,%46,%47,%48,%49,%50,%51,%52,%53,%54,%55,%56,%57,%58,%59,%60,%61,%62,%63}, {%64,%65,%66,%67}, rb, p, 1, 1, 1;\n}\n"
    : "+f"(d[0]),"+f"(d[1]),"+f"(d[2]),"+f"(d[3]),"+f"(d[4]),"+f"(d[5]),"+f"(d[6]),"+f"(d[7]),"+f"(d[8]),"+f"(d[9]),"+f"(d[10]),"+f"(d[11]),"+f"(d[12]),"+f"(d[13]),"+f"(d[14]),"+f"(d[15]),"+f"(d[16]),"+f"(d[17]),"+f"(d[18]),"+f"(d[19]),"+f"(d[20]),"+f"(d[21]),"+f"(d[22]),"+f"(d[23]),"+f"(d[24]),"+f"(d[25]),"+f"(d[26]),"+f"(d[27]),"+f"(d[28]),"+f"(d[29]),"+f"(d[30]),"+f"(d[31]),"+f"(d[32]),"+f"(d[33]),"+f"(d[34]),"+f"(d[35]),"+f"(d[36]),"+f"(d[37]),"+f"(d[38]),"+f"(d[39]),"+f"(d[40]),"+f"(d[41]),"+f"(d[42]),"+f"(d[43]),"+f"(d[44]),"+f"(d[45]),"+f"(d[46]),"+f"(d[47]),"+f"(d[48]),"+f"(d[49]),"+f"(d[50]),"+f"(d[51]),"+f"(d[52]),"+f"(d[53]),"+f"(d[54]),"+f"(d[55]),"+f"(d[56]),"+f"(d[57]),"+f"(d[58]),"+f"(d[59]),"+f"(d[60]),"+f"(d[61]),"+f"(d[62]),"+f"(d[63])
    : "r"(a[0]), "r"(a[1]), "r"(a[2]), "r"(a[3]), "r"(db), "r"(scaleD));
}

#define K1_STAGES 9
#define K1_STAGE_BYTES 16384
#define K1_OFF_ATT 0
#define K1_OFF_ST 62464
#define K1_OFF_XB8 (K1_OFF_ST + K1_STAGES * K1_STAGE_BYTES)
#define K1_OFF_BAR (K1_OFF_XB8 + 16384)
#define K1_SMEM (K1_OFF_BAR + 256 + 1024)
#define K1_NSTEPS 108
#define PP_OFF 5
#define K1_LATE 5
#define K1_CREGS 224
#define K1_PREGS 56
#define STR2(x) #x
#define STR(x) STR2(x)

__device__ __forceinline__ void ldmatrix_x4(uint32_t (&r)[4], uint32_t addr) {
  asm volatile("ldmatrix.sync.aligned.m8n8.x4.shared.b16 {%0,%1,%2,%3}, [%4];"
               : "=r"(r[0]), "=r"(r[1]), "=r"(r[2]), "=r"(r[3]) : "r"(addr) : "memory");
}

__global__ void __cluster_dims__(2, 1, 1) __launch_bounds__(384, 1)
k1_kernel(const __grid_constant__ CUtensorMap map_wg, const __grid_constant__ CUtensorMap map_wu,
          const __grid_constant__ CUtensorMap map_wqkv, const __grid_constant__ CUtensorMap map_x,
          const __nv_bfloat16* __restrict__ wd, const __nv_bfloat16* __restrict__ wo) {
  extern __shared__ uint8_t smem_raw[];
  const uint32_t sbase = (smem_u32(smem_raw) + 1023u) & ~1023u;
  uint8_t* sgen = smem_raw + (sbase - smem_u32(smem_raw));
  const int warp = threadIdx.x >> 5, lane = threadIdx.x & 31;
  const int crank = blockIdx.x & 1, peer = crank ^ 1;
  const int mt = 2 * (blockIdx.x >> 4) + crank, sp = (blockIdx.x >> 1) & 7;
  const uint32_t bar_full = sbase + K1_OFF_BAR, bar_empty = bar_full + 8 * K1_STAGES;
  const uint32_t bar_qkv = bar_empty + 8 * K1_STAGES;
  const uint32_t bar_x = bar_qkv + 8;
  if (threadIdx.x == 0) TL(0, 0);
  asm volatile("griddepcontrol.launch_dependents;" ::: "memory");

  if (threadIdx.x == 0) {
    for (int i = 0; i < K1_STAGES; i++) { mbar_init(bar_full + 8 * i, 1); mbar_init(bar_empty + 8 * i, 16); }
    mbar_init(bar_qkv, 8);
    mbar_init(bar_x, 1);
    asm volatile("fence.mbarrier_init.release.cluster;" ::: "memory");
    mbar_expect_tx(bar_x, 147456);
#pragma unroll 1
    for (int kb = 0; kb < 9; kb++) tma_load_2d(sbase + (kb < 8 ? kb * 16384 : K1_OFF_XB8), &map_x, kb * 64, mt * 128, bar_x);
  }
  __syncthreads();
  cluster_sync_all();

  if (warp >= 8) {
    asm volatile("setmaxnreg.dec.sync.aligned.u32 " STR(K1_PREGS) ";");
    if (warp == 8) {
      if (lane == 0) {
#pragma unroll 1
        for (int i = 0; i < K1_NSTEPS; i++) {
          const int s = (i + K1_LATE) % K1_STAGES, n = (i + K1_LATE) / K1_STAGES;
          mbar_wait(bar_empty + 8 * s, (n & 1) ^ 1);
          mbar_expect_tx(bar_full + 8 * s, 16384);
          const int c = i / 9, t = i - c * 9;
          const CUtensorMap* m = c < 3 ? &map_wqkv : (crank ? &map_wu : &map_wg);
          const int col = c < 3 ? c * 576 + 72 * sp + 64 * crank : sp * 576 + (c - 3) * 64;
          const uint32_t dst = sbase + K1_OFF_ST + s * K1_STAGE_BYTES + crank * 8192;
          tma_load_2d_mc(dst, m, col, t * 64, bar_full + 8 * s);
          tma_load_2d_mc(dst + 4096, m, col, t * 64 + 32, bar_full + 8 * s);
        }
      }
    } else {
      const int aw = warp - 9, at = threadIdx.x - 288;
      if (at == 0 && blockIdx.x < 32) g_cnt[blockIdx.x] = 0;
      mbar_wait(bar_qkv, 0);
      {
        uint4* dst = reinterpret_cast<uint4*>(g_halo) + (size_t)(mt * 8 + sp) * 288;
        for (int i = at; i < 288; i += 96) {
          const int blk = i / 36, c16 = i - blk * 36;
          dst[i] = *reinterpret_cast<const uint4*>(sgen + K1_OFF_ATT + (4 + blk) * 5184 + 128 * 36 + c16 * 16);
        }
        __threadfence();
        named_bar_sync(2, 96);
        if (at == 0) st_release(&g_flag[mt * 8 + sp], 1u);
      }
      if (mt > 0) {
        uint32_t spins = 0;
        while (ld_acquire(&g_flag[(mt - 1) * 8 + sp]) == 0) { if (++spins > (1u << 22)) break; __nanosleep(32); }
        const uint4* src = reinterpret_cast<const uint4*>(g_halo) + (size_t)((mt - 1) * 8 + sp) * 288;
        for (int i = at; i < 288; i += 96) {
          const int blk = i / 36, c16 = i - blk * 36;
          *reinterpret_cast<uint4*>(sgen + K1_OFF_ATT + (4 + blk) * 5184 + c16 * 16) = __ldcg(src + i);
        }
      }
      named_bar_sync(2, 96);
      if (threadIdx.x == 288) TL(0, 10);
      const float scale = 0.23570226039551584f;
      uint32_t* att = reinterpret_cast<uint32_t*>(sgen + K1_OFF_ATT);
#pragma unroll 1
      for (int item = at; item < 512; item += 96) {
        const int r = item & 127, hh = item >> 7;
        const int s = mt * 128 + r;
        uint32_t* qp = att + (hh * 144 + 16 + r) * 9;
        const uint32_t* kp = qp + 4 * 144 * 9;
        const uint32_t* vp = kp + 4 * 144 * 9;
        const int nw = s >= 14 ? 8 : (s >> 1) + 1;
        uint32_t qw[9];
#pragma unroll
        for (int i = 0; i < 9; i++) qw[i] = qp[i];
        float lg[8];
#pragma unroll
        for (int w = 0; w < 8; w++) {
          const uint32_t* p = kp - (w < nw ? w : 0) * 18;
          float acc = 0.f;
#pragma unroll
          for (int i = 0; i < 9; i++) { const uint32_t u = p[i]; acc += bf_lo(qw[i]) * bf_lo(u) + bf_hi(qw[i]) * bf_hi(u); }
          lg[w] = w < nw ? acc * scale : -1e9f;
        }
        float m = lg[0];
#pragma unroll
        for (int w = 1; w < 8; w++) m = fmaxf(m, lg[w]);
        float sum = 0.f;
#pragma unroll
        for (int w = 0; w < 8; w++) { lg[w] = __expf(lg[w] - m); sum += lg[w]; }
        const float inv = 1.0f / sum;
        float o[18];
#pragma unroll
        for (int i = 0; i < 18; i++) o[i] = 0.f;
#pragma unroll
        for (int w = 0; w < 8; w++) {
          const uint32_t* p = vp - (w < nw ? w : 0) * 18;
          const float a = lg[w] * inv;
#pragma unroll
          for (int i = 0; i < 9; i++) { const uint32_t u = p[i]; o[2 * i] += a * bf_lo(u); o[2 * i + 1] += a * bf_hi(u); }
        }
#pragma unroll
        for (int i = 0; i < 9; i++) qp[i] = pack_bf16(o[2 * i], o[2 * i + 1]);
      }
      named_bar_sync(2, 96);
      {
        uint32_t* go = reinterpret_cast<uint32_t*>(g_o) + (size_t)mt * 128 * 288 + sp * 36;
        for (int i = at; i < 128 * 36; i += 96) {
          const int r = i / 36, w = i - r * 36, hh = w / 9, dd = w - hh * 9;
          go[r * 288 + w] = att[(hh * 144 + 16 + r) * 9 + dd];
        }
      }
      if (threadIdx.x == 288) TL(0, 11);
      if (aw == 0) {
        if (lane < 8) l2_prefetch((const char*)wd + (size_t)blockIdx.x * 41472 + lane * 5184, 5184);
        else if (lane == 8) l2_prefetch((const char*)wo + (size_t)blockIdx.x * 5184, 5184);
      }
    }
    __syncwarp();
    cluster_sync_all();
    return;
  }

  asm volatile("setmaxnreg.inc.sync.aligned.u32 " STR(K1_CREGS) ";");
  const int wg_ = warp >> 2;
  const int lrow = wg_ * 64 + (warp & 3) * 16 + (lane >> 2);
  const int tq = lane & 3;
  uint32_t a[32][4];
  mbar_wait(bar_x, 0);
  if (threadIdx.x == 0) TL(0, 14);
  {
    const int mrow = warp * 16 + ((lane >> 3) & 1) * 8 + (lane & 7);
    const uint32_t rbase = sbase + mrow * 128;
    const uint32_t sw0 = ((lane >> 4) ^ (mrow & 7)) << 4;
#define K1_XADDR(kk) (rbase + ((kk) < 32 ? ((kk) >> 2) * 16384 : K1_OFF_XB8) + (sw0 ^ (((kk) & 3) << 5)))
    float s0 = 0.f, s1 = 0.f, q0 = 0.f, q1 = 0.f, s0b = 0.f, s1b = 0.f, q0b = 0.f, q1b = 0.f, p0, p1;
    {
      uint32_t v[4];
      ldmatrix_x4(v, K1_XADDR(0));
      p0 = __shfl_sync(0xffffffffu, bf_lo(v[0]), lane & ~3);
      p1 = __shfl_sync(0xffffffffu, bf_lo(v[1]), lane & ~3);
    }
#pragma unroll 4
    for (int kk = 0; kk < 36; kk++) {
      uint32_t v[4];
      ldmatrix_x4(v, K1_XADDR(kk));
      float d;
      d = bf_lo(v[0]) - p0; s0 += d; q0 = fmaf(d, d, q0);  d = bf_hi(v[0]) - p0; s0b += d; q0b = fmaf(d, d, q0b);
      d = bf_lo(v[2]) - p0; s0 += d; q0 = fmaf(d, d, q0);  d = bf_hi(v[2]) - p0; s0b += d; q0b = fmaf(d, d, q0b);
      d = bf_lo(v[1]) - p1; s1 += d; q1 = fmaf(d, d, q1);  d = bf_hi(v[1]) - p1; s1b += d; q1b = fmaf(d, d, q1b);
      d = bf_lo(v[3]) - p1; s1 += d; q1 = fmaf(d, d, q1);  d = bf_hi(v[3]) - p1; s1b += d; q1b = fmaf(d, d, q1b);
    }
    s0 += s0b; s1 += s1b; q0 += q0b; q1 += q1b;
#pragma unroll
    for (int o = 1; o < 4; o <<= 1) {
      s0 += __shfl_xor_sync(0xffffffffu, s0, o); s1 += __shfl_xor_sync(0xffffffffu, s1, o);
      q0 += __shfl_xor_sync(0xffffffffu, q0, o); q1 += __shfl_xor_sync(0xffffffffu, q1, o);
    }
    s0 *= (1.0f / DM); s1 *= (1.0f / DM);
    const float m0 = p0 + s0, m1 = p1 + s1;
    const float r0 = rsqrtf(fmaxf(q0 * (1.0f / DM) - s0 * s0, 0.f) + 1e-5f), r1 = rsqrtf(fmaxf(q1 * (1.0f / DM) - s1 * s1, 0.f) + 1e-5f);
    const float b0 = -m0 * r0, b1 = -m1 * r1;
#pragma unroll
    for (int kk = 0; kk < 36; kk++) {
      uint32_t v[4];
      ldmatrix_x4(v, K1_XADDR(kk));
      v[0] = pack_bf16(fmaf(bf_lo(v[0]), r0, b0), fmaf(bf_hi(v[0]), r0, b0));
      v[2] = pack_bf16(fmaf(bf_lo(v[2]), r0, b0), fmaf(bf_hi(v[2]), r0, b0));
      v[1] = pack_bf16(fmaf(bf_lo(v[1]), r1, b1), fmaf(bf_hi(v[1]), r1, b1));
      v[3] = pack_bf16(fmaf(bf_lo(v[3]), r1, b1), fmaf(bf_hi(v[3]), r1, b1));
      if (kk < 32) { a[kk & 31][0] = v[0]; a[kk & 31][1] = v[1]; a[kk & 31][2] = v[2]; a[kk & 31][3] = v[3]; }
      else stmatrix_x4(K1_XADDR(kk), v[0], v[1], v[2], v[3]);
    }
    fence_async_smem();
    __syncwarp();
    if (lane == 0) {
#pragma unroll
      for (int s = 0; s < K1_LATE; s++) mbar_arrive_both(bar_empty + 8 * s, peer);
    }
  }
  named_bar_sync(1, 256);
  if (threadIdx.x == 0) TL(0, 1);

  const uint32_t a8_lo = make_desc(sbase + K1_OFF_XB8 + wg_ * 8192, 16, 1024);
  const uint32_t b_lo0 = make_desc(sbase + K1_OFF_ST, 8192, 1024);
  int s_cur = K1_LATE;
  uint32_t nwrap = 0;
#define K1_FULL_PAR(s, n) (((s) >= K1_LATE ? (n) : (n) - 1) & 1)
#define K1_ADVANCE() do { if (++s_cur == K1_STAGES) { s_cur = 0; nwrap++; } } while (0)

  if (wg_ == 1) named_bar_sync(3, 256);
#pragma unroll 1
  for (int part = 0; part < 3; part++) {
    float d[36];
#pragma unroll
    for (int t = 0; t < 9; t++) {
      if (t == PP_OFF && part == 0 && wg_ == 0) asm volatile("bar.arrive 3, 256;" ::: "memory");
      mbar_wait(bar_full + 8 * s_cur, K1_FULL_PAR(s_cur, nwrap));
      const uint32_t bs = b_lo0 + s_cur * (K1_STAGE_BYTES >> 4);
      wgmma_fence();
#pragma unroll
      for (int kk = 0; kk < 4; kk++) {
        if (t < 8) wgmma_rs_n72(d, a[(4 * t + kk) & 31], bs + kk * 128, (t > 0) | (kk > 0));
        else wgmma_n72(d, a8_lo + kk * 2, bs + kk * 128, 1);
      }
      wgmma_commit();
      if (t > 0) {
        wgmma_wait<1>();
        if (lane == 0) mbar_arrive_both(bar_empty + 8 * (s_cur == 0 ? K1_STAGES - 1 : s_cur - 1), peer);
      }
      K1_ADVANCE();
    }
    wgmma_wait<0>();
    if (lane == 0) mbar_arrive_both(bar_empty + 8 * (s_cur == 0 ? K1_STAGES - 1 : s_cur - 1), peer);
#pragma unroll
    for (int j = 0; j < 9; j++) {
      const int c = 8 * j + 2 * tq, hh = c / 18, dd = c - hh * 18;
      uint8_t* p = sgen + K1_OFF_ATT + (part * 4 + hh) * 5184 + (16 + lrow) * 36 + dd * 2;
      *reinterpret_cast<uint32_t*>(p) = pack_bf16(d[4 * j], d[4 * j + 1]);
      *reinterpret_cast<uint32_t*>(p + 8 * 36) = pack_bf16(d[4 * j + 2], d[4 * j + 3]);
    }
  }
  __syncwarp();
  if (lane == 0) mbar_arrive(bar_qkv);
  if (threadIdx.x == 0) TL(0, 3);

  uint8_t* hblob = reinterpret_cast<uint8_t*>(g_h) + ((size_t)mt * 72 + sp * 9) * 16384 + lrow * 128;
  const int sw = lrow & 7;
#pragma unroll 1
  for (int c = 0; c < 9; c++) {
    float d[64];
#pragma unroll
    for (int t = 0; t < 9; t++) {
      mbar_wait(bar_full + 8 * s_cur, K1_FULL_PAR(s_cur, nwrap));
      const uint32_t bs = b_lo0 + s_cur * (K1_STAGE_BYTES >> 4);
      wgmma_fence();
#pragma unroll
      for (int kk = 0; kk < 4; kk++) {
        if (t < 8) wgmma_rs_n128(d, a[(4 * t + kk) & 31], bs + kk * 128, (t > 0) | (kk > 0));
        else wgmma_n128(d, a8_lo + kk * 2, bs + kk * 128, 1);
      }
      wgmma_commit();
      if (t > 0) {
        wgmma_wait<1>();
        if (lane == 0) mbar_arrive_both(bar_empty + 8 * (s_cur == 0 ? K1_STAGES - 1 : s_cur - 1), peer);
      }
      K1_ADVANCE();
    }
    wgmma_wait<0>();
    if (lane == 0) mbar_arrive_both(bar_empty + 8 * (s_cur == 0 ? K1_STAGES - 1 : s_cur - 1), peer);
    if (threadIdx.x == 0 && c < 5) TL(0, 4 + c);
#pragma unroll
    for (int G = 0; G < 2; G++) {
      uint8_t* p = hblob + c * 16384 + (((G * 4 + tq) ^ sw) << 4);
#pragma unroll
      for (int hf = 0; hf < 2; hf++) {
        uint32_t w[4];
#pragma unroll
        for (int aa = 0; aa < 4; aa++) {
          const int i = 4 * (4 * G + aa) + 2 * hf;
          w[aa] = pack_bf16(fmaxf(d[i], 0.f) * d[32 + i], fmaxf(d[i + 1], 0.f) * d[32 + i + 1]);
        }
        *reinterpret_cast<uint4*>(p + hf * 1024) = make_uint4(w[0], w[1], w[2], w[3]);
      }
    }
  }
  if (threadIdx.x == 0) TL(0, 9);
  __syncwarp();
  cluster_sync_all();
}

#define K3_STAGES 4
#define K3_STAGE_BYTES (16384 + 5 * 8192)
#define K3_OFF_BAR (K3_STAGES * K3_STAGE_BYTES)
#define K3_SMEM (K3_OFF_BAR + 128 + 1024)

#define K3_ACC(J, i) ((J) < 24 ? d0[(4 * (J) + (i)) % 96] : d1[(4 * ((J) - 24) + (i)) % 48])
#define K3_PK(J, h) pack_bf16(K3_ACC(J, 2 * (h)), K3_ACC(J, 2 * (h) + 1))
template <int Q>
__device__ __forceinline__ void k3_reduce(float (&d0)[96], float (&d1)[48], int tile, int mt, int nh, int r, int lane,
                                          const __nv_bfloat16* __restrict__ x, __nv_bfloat16* __restrict__ out) {
  uint4* mine = reinterpret_cast<uint4*>(g_part) + (size_t)(tile * 4 + Q) * (4 * 5 * 256) + threadIdx.x;
#pragma unroll
  for (int D = 0; D < 4; D++) {
    if (D != Q) {
#pragma unroll
      for (int k = 0; k < 4; k++)
        __stcg(mine + (D * 5 + k) * 256, make_uint4(K3_PK(9 * D + 2 * k, 0), K3_PK(9 * D + 2 * k, 1), K3_PK(9 * D + 2 * k + 1, 0), K3_PK(9 * D + 2 * k + 1, 1)));
      __stcg(reinterpret_cast<uint2*>(mine + (D * 5 + 4) * 256), make_uint2(K3_PK(9 * D + 8, 0), K3_PK(9 * D + 8, 1)));
    }
  }
  __threadfence();
  named_bar_sync(1, 256);
  if (threadIdx.x == 0) {
    red_release_add(&g_cnt[tile], 1u);
    TL(1, 3);
    uint32_t spins = 0;
    while (ld_acquire(&g_cnt[tile]) < 4u) { if (++spins > (1u << 22)) break; }
    TL(1, 4);
  }
  const size_t go = (size_t)(mt * 128 + r) * DM + nh * 288 + 2 * (lane & 3) + 72 * Q;
  uint32_t x0[9], x1[9];
#pragma unroll
  for (int j = 0; j < 9; j++) {
    x0[j] = *reinterpret_cast<const uint32_t*>(x + go + 8 * j);
    x1[j] = *reinterpret_cast<const uint32_t*>(x + go + 8 * DM + 8 * j);
  }
  named_bar_sync(1, 256);
  if (threadIdx.x == 0) TL(1, 6);
  float a[9][4];
#pragma unroll
  for (int j = 0; j < 9; j++) {
#pragma unroll
    for (int i = 0; i < 4; i++) a[j][i] = K3_ACC(9 * Q + j, i);
  }
  uint4 u[3][5];
#pragma unroll
  for (int si = 0; si < 3; si++) {
    const int src = si < Q ? si : si + 1;
    const uint4* p = reinterpret_cast<const uint4*>(g_part) + (size_t)(tile * 4 + src) * (4 * 5 * 256) + (Q * 5) * 256 + threadIdx.x;
#pragma unroll
    for (int k = 0; k < 4; k++) u[si][k] = __ldcg(p + k * 256);
    const uint2 t = __ldcg(reinterpret_cast<const uint2*>(p + 4 * 256));
    u[si][4] = make_uint4(t.x, t.y, 0, 0);
  }
#pragma unroll
  for (int si = 0; si < 3; si++) {
#pragma unroll
    for (int k = 0; k < 5; k++) {
      a[2 * k][0] += bf_lo(u[si][k].x); a[2 * k][1] += bf_hi(u[si][k].x); a[2 * k][2] += bf_lo(u[si][k].y); a[2 * k][3] += bf_hi(u[si][k].y);
      if (k < 4) { a[2 * k + 1][0] += bf_lo(u[si][k].z); a[2 * k + 1][1] += bf_hi(u[si][k].z); a[2 * k + 1][2] += bf_lo(u[si][k].w); a[2 * k + 1][3] += bf_hi(u[si][k].w); }
    }
  }
#pragma unroll
  for (int j = 0; j < 9; j++) {
    *reinterpret_cast<uint32_t*>(out + go + 8 * j) = pack_bf16(a[j][0] + bf_lo(x0[j]), a[j][1] + bf_hi(x0[j]));
    *reinterpret_cast<uint32_t*>(out + go + 8 * DM + 8 * j) = pack_bf16(a[j][2] + bf_lo(x1[j]), a[j][3] + bf_hi(x1[j]));
  }
}

__global__ void __cluster_dims__(2, 1, 1) __launch_bounds__(384, 1)
k3_kernel(const __grid_constant__ CUtensorMap map_o, const __grid_constant__ CUtensorMap map_wd5,
          const __grid_constant__ CUtensorMap map_wo, const __nv_bfloat16* __restrict__ x, __nv_bfloat16* __restrict__ out) {
  extern __shared__ uint8_t smem_raw[];
  const uint32_t sbase = (smem_u32(smem_raw) + 1023u) & ~1023u;
  const int warp = threadIdx.x >> 5, lane = threadIdx.x & 31;
  const int crank = blockIdx.x & 1, peer = crank ^ 1;
  const int ks = (blockIdx.x >> 1) & 3, nh = (blockIdx.x >> 3) & 1;
  const int mt = 2 * (blockIdx.x >> 4) + crank;
  const int tile = mt * 2 + nh;
  const int g0 = ks == 0 ? 0 : 1 + 20 * ks;
  const int nsteps = ks == 0 ? 21 : 20;
  const uint32_t bar_full = sbase + K3_OFF_BAR, bar_empty = bar_full + 8 * K3_STAGES;
  if (threadIdx.x == 0) TL(1, 0);

  if (threadIdx.x == 0) {
    for (int i = 0; i < K3_STAGES; i++) { mbar_init(bar_full + 8 * i, 1); mbar_init(bar_empty + 8 * i, 16); }
    asm volatile("fence.mbarrier_init.release.cluster;" ::: "memory");
  }
  __syncthreads();
  cluster_sync_all();

  if (warp >= 8) {
    asm volatile("setmaxnreg.dec.sync.aligned.u32 40;");
    if (warp == 8 && lane == 0) {
      for (int it = 0; it < K3_STAGES; it++) {
        mbar_expect_tx(bar_full + 8 * it, K3_STAGE_BYTES);
        const uint32_t dst = sbase + it * K3_STAGE_BYTES;
#pragma unroll
        for (int b = 0; b < 5; b++)
          tma_load_5d_mc(dst + 16384 + b * 8192 + crank * 4096, &map_wd5, nh * 288 + b * 64, 2 * (g0 + it) + crank, bar_full + 8 * it);
      }
      asm volatile("griddepcontrol.wait;" ::: "memory");
      for (int it = 0; it < K3_STAGES; it++)
        bulk_load_1d(sbase + it * K3_STAGE_BYTES, reinterpret_cast<const uint8_t*>(g_h) + ((size_t)mt * 72 + g0 + it) * 16384, 16384, bar_full + 8 * it);
      for (int it = K3_STAGES; it < nsteps; it++) {
        int st = it % K3_STAGES; uint32_t ph = (it / K3_STAGES) & 1;
        mbar_wait(bar_empty + 8 * st, ph ^ 1);
        mbar_expect_tx(bar_full + 8 * st, K3_STAGE_BYTES);
        uint32_t dst = sbase + st * K3_STAGE_BYTES;
        const int g = g0 + it;
        if (g < 72) {
          bulk_load_1d(dst, reinterpret_cast<const uint8_t*>(g_h) + ((size_t)mt * 72 + g) * 16384, 16384, bar_full + 8 * st);
#pragma unroll
          for (int b = 0; b < 5; b++)
            tma_load_5d_mc(dst + 16384 + b * 8192 + crank * 4096, &map_wd5, nh * 288 + b * 64, 2 * g + crank, bar_full + 8 * st);
        } else {
          const int kk = (g - 72) * 64;
          tma_load_2d(dst, &map_o, kk, mt * 128, bar_full + 8 * st);
#pragma unroll
          for (int b = 0; b < 5; b++)
            tma_load_2d_mc(dst + 16384 + b * 8192 + crank * 4096, &map_wo, nh * 288 + b * 64, kk + crank * 32, bar_full + 8 * st);
        }
      }
    }
    if (warp == 9 && lane == 0) {
      asm volatile("griddepcontrol.wait;" ::: "memory");
      g_flag[blockIdx.x] = 0;
    }
    __syncwarp();
    cluster_sync_all();
  } else {
    asm volatile("setmaxnreg.inc.sync.aligned.u32 232;");
    const int wg = warp >> 2;
    float d0[96], d1[48];
    for (int it = 0; it < nsteps; it++) {
      int st = it % K3_STAGES; uint32_t ph = (it / K3_STAGES) & 1;
      mbar_wait(bar_full + 8 * st, ph);
      if (threadIdx.x == 0 && it == 0) TL(1, 1);
      uint32_t as = sbase + st * K3_STAGE_BYTES + wg * 8192;
      uint32_t bs = sbase + st * K3_STAGE_BYTES + 16384;
      wgmma_fence();
#pragma unroll
      for (int kk = 0; kk < 4; kk++) {
        uint32_t da = make_desc(as + kk * 32, 16, 1024);
        wgmma_n192(d0, da, make_desc(bs + kk * 2048, 8192, 1024), (it > 0) | (kk > 0));
        wgmma_n96(d1, da, make_desc(bs + 3 * 8192 + kk * 2048, 8192, 1024), (it > 0) | (kk > 0));
      }
      wgmma_commit();
      if (it > 0) {
        wgmma_wait<1>();
        if (lane == 0) mbar_arrive_both(bar_empty + 8 * ((it - 1) % K3_STAGES), peer);
      }
    }
    wgmma_wait<0>();
    if (threadIdx.x == 0) TL(1, 2);
    const int r = wg * 64 + (warp & 3) * 16 + (lane >> 2);
    if (ks == 0) k3_reduce<0>(d0, d1, tile, mt, nh, r, lane, x, out);
    else if (ks == 1) k3_reduce<1>(d0, d1, tile, mt, nh, r, lane, x, out);
    else if (ks == 2) k3_reduce<2>(d0, d1, tile, mt, nh, r, lane, x, out);
    else k3_reduce<3>(d0, d1, tile, mt, nh, r, lane, x, out);
    if (threadIdx.x == 0) TL(1, 5);
    __syncwarp();
    cluster_sync_all();
  }
}

typedef CUresult (*PFN_encodeTiled)(CUtensorMap*, CUtensorMapDataType, cuuint32_t, void*, const cuuint64_t*,
                                    const cuuint64_t*, const cuuint32_t*, const cuuint32_t*, CUtensorMapInterleave,
                                    CUtensorMapSwizzle, CUtensorMapL2promotion, CUtensorMapFloatOOBfill);

static void make_map(PFN_encodeTiled fn, CUtensorMap* m, const void* ptr, uint64_t rows, uint64_t cols, uint32_t box_rows,
                     uint32_t box_cols) {
  cuuint64_t dims[2] = {cols, rows};
  cuuint64_t strides[1] = {cols * 2};
  cuuint32_t box[2] = {box_cols, box_rows};
  cuuint32_t es[2] = {1, 1};
  fn(m, CU_TENSOR_MAP_DATA_TYPE_BFLOAT16, 2, const_cast<void*>(ptr), dims, strides, box, es, CU_TENSOR_MAP_INTERLEAVE_NONE,
     CU_TENSOR_MAP_SWIZZLE_128B, CU_TENSOR_MAP_L2_PROMOTION_L2_256B, CU_TENSOR_MAP_FLOAT_OOB_FILL_NONE);
}

extern "C" void kernel_launch(void* const* d_in, const int* in_sizes, int n_in, void* d_out, int out_size) {
  const __nv_bfloat16* x = (const __nv_bfloat16*)d_in[0];
  const __nv_bfloat16* wqkv = (const __nv_bfloat16*)d_in[1];
  const __nv_bfloat16* wo = (const __nv_bfloat16*)d_in[2];
  const __nv_bfloat16* wg = (const __nv_bfloat16*)d_in[4];
  const __nv_bfloat16* wu = (const __nv_bfloat16*)d_in[5];
  const __nv_bfloat16* wd = (const __nv_bfloat16*)d_in[6];
  __nv_bfloat16* out = (__nv_bfloat16*)d_out;

  static PFN_encodeTiled enc = nullptr;
  static void* p_o = nullptr;
  if (!enc) {
    void* fp = nullptr;
    cudaDriverEntryPointQueryResult qr;
    cudaGetDriverEntryPoint("cuTensorMapEncodeTiled", &fp, cudaEnableDefault, &qr);
    enc = (PFN_encodeTiled)fp;
    cudaGetSymbolAddress(&p_o, g_o);
    cudaFuncSetAttribute(k1_kernel, cudaFuncAttributeMaxDynamicSharedMemorySize, K1_SMEM);
    cudaFuncSetAttribute(k3_kernel, cudaFuncAttributeMaxDynamicSharedMemorySize, K3_SMEM);
  }
  CUtensorMap m_wg, m_wu, m_wqkv, m_o, m_wd5, m_wo, m_x;
  make_map(enc, &m_x, x, S_LEN, DM, 128, 64);
  make_map(enc, &m_wg, wg, DM, FF, 32, 64);
  make_map(enc, &m_wu, wu, DM, FF, 32, 64);
  make_map(enc, &m_wqkv, wqkv, DM, NQKV, 32, 64);
  make_map(enc, &m_o, p_o, S_LEN, DM, 128, 64);
  make_map(enc, &m_wo, wo, DM, DM, 32, 64);
  {
    cuuint64_t dims[5] = {DM, 2, 4, 4, FF / 32};
    cuuint64_t strides[4] = {1152, 8 * 1152, 2 * 1152, 32 * 1152};
    cuuint32_t box[5] = {64, 2, 4, 4, 1};
    cuuint32_t es[5] = {1, 1, 1, 1, 1};
    enc(&m_wd5, CU_TENSOR_MAP_DATA_TYPE_BFLOAT16, 5, const_cast<__nv_bfloat16*>(wd), dims, strides, box, es,
        CU_TENSOR_MAP_INTERLEAVE_NONE, CU_TENSOR_MAP_SWIZZLE_128B, CU_TENSOR_MAP_L2_PROMOTION_L2_256B,
        CU_TENSOR_MAP_FLOAT_OOB_FILL_NONE);
  }

  k1_kernel<<<128, 384, K1_SMEM>>>(m_wg, m_wu, m_wqkv, m_x, wd, wo);
  {
    cudaLaunchConfig_t cfg = {};
    cfg.gridDim = dim3(128); cfg.blockDim = dim3(384); cfg.dynamicSmemBytes = K3_SMEM; cfg.stream = cudaStreamPerThread;
    cudaLaunchAttribute at[1];
    at[0].id = cudaLaunchAttributeProgrammaticStreamSerialization;
    at[0].val.programmaticStreamSerializationAllowed = 1;
    cfg.attrs = at; cfg.numAttrs = 1;
    cudaLaunchKernelEx(&cfg, k3_kernel, m_o, m_wd5, m_wo, x, out);
  }
}
```
